```python
import torch

def _softmax(x, axis=-1):
    return torch.softmax(x, dim=axis)
def _gelu(x):
    return torch.nn.functional.gelu(x, approximate="tanh")
def _silu(x):
    return torch.nn.functional.silu(x)
def _sigmoid(x):
    return torch.sigmoid(x)
def _layernorm(x, axis=-1, eps=1e-5):
    m = x.mean(dim=axis, keepdim=True)
    v = x.var(dim=axis, keepdim=True, unbiased=False)
    return (x - m) / torch.sqrt(v + eps)
def _scatter_add(tgt, idx, src, axis=0):
    return tgt.clone().index_add_(axis, idx, src)
def _segment_sum(src, seg, n):
    out = torch.zeros((n,) + src.shape[1:], dtype=src.dtype)
    return out.index_add_(0, seg, src)
def _pad(x, pw):
    flat = tuple(v for pair in reversed(pw) for v in pair)
    return torch.nn.functional.pad(x, flat)

kernel_name = 'parallel_sum__gqa_block_cached__geglu_ffn__decode'

def setup_inputs():

    _w = (lambda a: (lambda t: t.to(torch.bfloat16) if t.is_floating_point() else t)(torch.as_tensor(a)))
    def _A_setup():
        B, Sq, D = 2, 1, 1024
        Hq, Hkv, Sk, Dh = 32, 4, 32768, 128
        assert Hq % Hkv == 0, (Hq, Hkv)
        return {
            "x": _w((lambda *s: torch.randn(*s, dtype=torch.bfloat16) * 0.05)(B, Sq, D)),
            "k_cache": _w((lambda *s: torch.randn(*s, dtype=torch.bfloat16) * 3.2)(B, Hkv, Sk, Dh)),
            "v_cache": _w((lambda *s: torch.randn(*s, dtype=torch.bfloat16) * 1.6)(B, Hkv, Sk, Dh)),
            "wq": _w((lambda *s: torch.randn(*s, dtype=torch.bfloat16) * 3.2)(D, Hq * Dh) * (D ** -0.5)),
            "wo": _w((lambda *s: torch.randn(*s, dtype=torch.bfloat16) * 1.6)(Hq * Dh, D) * ((Hq * Dh) ** -0.5)),
        }
    _A_in = _A_setup()

    def _B_setup():
        B, S, D, F = 2, 1, 1024, 3584
        return {
            "x": _w((lambda *s: torch.randn(*s, dtype=torch.bfloat16) * 0.05)(B, S, D)),
            "w_gate": _w((lambda *s: torch.randn(*s, dtype=torch.bfloat16) * 0.05)(D, F)),
            "w_up": _w((lambda *s: torch.randn(*s, dtype=torch.bfloat16) * 0.05)(D, F)),
            "w_down": _w((lambda *s: torch.randn(*s, dtype=torch.bfloat16) * 0.05)(F, D)),
        }
    _B_in = _B_setup()

    return {
        "A_x": _A_in["x"],
        "A_k_cache": _A_in["k_cache"],
        "A_v_cache": _A_in["v_cache"],
        "A_wq": _A_in["wq"],
        "A_wo": _A_in["wo"],
        "B_x": _B_in["x"],
        "B_w_gate": _B_in["w_gate"],
        "B_w_up": _B_in["w_up"],
        "B_w_down": _B_in["w_down"],
    }

def reference(A_x, A_k_cache, A_v_cache, A_wq, A_wo, B_x, B_w_gate, B_w_up, B_w_down):
    def _A_ref(x, k_cache, v_cache, wq, wo):
        B, Sq, D = x.shape
        Hq, Dh = 32, 128
        Hkv = k_cache.shape[1]
        rep = Hq // Hkv
        q = (lambda x, *d: x.permute(*d))((x @ wq).reshape(B, Sq, Hq, Dh), 0, 2, 1, 3)
        k = (lambda x, n, axis: torch.repeat_interleave(x, n, dim=axis))(k_cache, rep, axis=1)
        v = (lambda x, n, axis: torch.repeat_interleave(x, n, dim=axis))(v_cache, rep, axis=1)
        scores = torch.einsum("bhqd,bhkd->bhqk", q, k) * (Dh ** -0.5)
        p = _softmax(scores, axis=-1)
        o = torch.einsum("bhqk,bhkd->bhqd", p, v)
        return (lambda x, *d: x.permute(*d))(o, 0, 2, 1, 3).reshape(B, Sq, Hq * Dh) @ wo

    def _B_ref(x, w_gate, w_up, w_down):
        return (_gelu(x @ w_gate) * (x @ w_up)) @ w_down

    x = A_x
    xn = _layernorm(x, axis=-1)
    return x + _A_ref(xn, A_k_cache, A_v_cache, A_wq, A_wo) + _B_ref(xn, B_w_gate, B_w_up, B_w_down)
```

```cpp
#include <cuda_runtime.h>
#include <cuda.h>
#include <cuda_bf16.h>
#include <stdint.h>

namespace {

constexpr int NCTA      = 128;
constexpr int NTHREADS  = 320;
constexpr int SLOT      = 16384;
#define NSLOT_ 10
constexpr int NSLOT     = NSLOT_;
constexpr int N_ITEMS   = 84;
constexpr int IT_WG     = 4;
constexpr int IT_KV     = 8;
constexpr int IT_WU     = 72;
constexpr int IT_WO     = 76;
constexpr int IT_WD     = 80;
constexpr int BURST     = 2;
constexpr int NFFN      = 112;
constexpr uint32_t POLL_LIMIT = 1u << 22;
constexpr int PO_ROW    = 136;

constexpr int SM_RED    = NSLOT * SLOT;
constexpr int SM_Q      = SM_RED + 8 * 8 * 132 * 4;
constexpr int SM_G      = SM_Q + 8 * 136 * 2;
constexpr int SM_ML     = SM_G + 3 * 8 * 32 * 2 * 4;
constexpr int SM_H      = SM_ML + 8 * 8 * 2 * 4;
constexpr int SM_X      = SM_H + 2 * 464 * 2;
constexpr int SM_LN     = SM_X + 2 * 1032 * 2;
constexpr int SM_ISS    = SM_LN + 80;
constexpr int SM_BAR    = SM_ISS + 64;
constexpr int SM_TOTAL  = SM_BAR + 2 * NSLOT * 8;
constexpr int SMEM_BYTES = SM_TOTAL + 1024;

struct Params {
    CUtensorMap m[7];
    const __nv_bfloat16* x;
    __nv_bfloat16* out;
    int pace_ns;
    int burst;
    int inflight;
    int backoff;
    int opt, opt2, opt3;
    int stag_grp, stag_j;
    int stall_lat, stall_ns;
    int stall_from, stall_to;
};

__device__ uint32_t g_epoch;
__device__ __align__(128) uint32_t g_q[2 * 4096];
__device__ __align__(128) uint32_t g_h[2 * 4096];
__device__ __align__(128) uint32_t g_o[8 * 1024];
__device__ __align__(128) uint32_t g_po[NCTA * 8 * PO_ROW];
__device__ __align__(128) uint32_t g_pout[NCTA * 256];

__device__ __forceinline__ uint32_t smem_u32(const void* p) { return (uint32_t)__cvta_generic_to_shared(p); }
__device__ __forceinline__ unsigned long long gtime() { unsigned long long t; asm volatile("mov.u64 %0, %globaltimer;" : "=l"(t)); return t; }
__device__ __forceinline__ uint32_t gtime32() { uint32_t t; asm volatile("mov.u32 %0, %globaltimer_lo;" : "=r"(t)); return t; }
__device__ __forceinline__ void mbar_init(uint32_t bar, uint32_t cnt) { asm volatile("mbarrier.init.shared::cta.b64 [%0], %1;" :: "r"(bar), "r"(cnt) : "memory"); }
__device__ __forceinline__ void mbar_expect_tx(uint32_t bar, uint32_t bytes) { asm volatile("mbarrier.arrive.expect_tx.shared::cta.b64 _, [%0], %1;" :: "r"(bar), "r"(bytes) : "memory"); }
__device__ __forceinline__ void mbar_arrive(uint32_t bar, uint32_t cnt) { asm volatile("mbarrier.arrive.shared::cta.b64 _, [%0], %1;" :: "r"(bar), "r"(cnt) : "memory"); }
__device__ __forceinline__ void mbar_wait(uint32_t bar, uint32_t parity) {
    asm volatile("{\n.reg .pred p;\n.reg .u32 n;\nmov.u32 n, 0;\n"
                 "W_LOOP:\nmbarrier.try_wait.parity.shared::cta.b64 p, [%0], %1;\n@p bra W_DONE;\n"
                 "add.u32 n, n, 1;\nsetp.lt.u32 p, n, %2;\n@p bra W_LOOP;\ntrap;\nW_DONE:\n}"
                 :: "r"(bar), "r"(parity), "n"(POLL_LIMIT >> 2) : "memory");
}
__device__ __forceinline__ bool mbar_test(uint32_t bar, uint32_t parity) {
    uint32_t ok;
    asm volatile("{\n.reg .pred p;\nmbarrier.test_wait.parity.shared::cta.b64 p, [%1], %2;\nselp.u32 %0, 1, 0, p;\n}" : "=r"(ok) : "r"(bar), "r"(parity) : "memory");
    return ok;
}
__device__ __forceinline__ void tma3d(uint32_t dst, const CUtensorMap* m, int c0, int c1, uint32_t bar, uint64_t pol) {
    asm volatile("cp.async.bulk.tensor.3d.shared::cluster.global.mbarrier::complete_tx::bytes.L2::cache_hint [%0], [%1, {%3, %4, %5}], [%2], %6;"
                 :: "r"(dst), "l"(m), "r"(bar), "r"(c0), "r"(c1), "r"(0), "l"(pol) : "memory");
}
__device__ __forceinline__ void cbar() { asm volatile("bar.sync 1, 256;" ::: "memory"); }

__device__ __forceinline__ void ldsm4(uint32_t (&r)[4], uint32_t a) {
    asm volatile("ldmatrix.sync.aligned.m8n8.x4.shared.b16 {%0,%1,%2,%3}, [%4];" : "=r"(r[0]), "=r"(r[1]), "=r"(r[2]), "=r"(r[3]) : "r"(a) : "memory");
}
__device__ __forceinline__ void ldsm4t(uint32_t (&r)[4], uint32_t a) {
    asm volatile("ldmatrix.sync.aligned.m8n8.x4.trans.shared.b16 {%0,%1,%2,%3}, [%4];" : "=r"(r[0]), "=r"(r[1]), "=r"(r[2]), "=r"(r[3]) : "r"(a) : "memory");
}
__device__ __forceinline__ void mma16816(float (&c)[4], const uint32_t (&a)[4], uint32_t b0, uint32_t b1) {
    asm("mma.sync.aligned.m16n8k16.row.col.f32.bf16.bf16.f32 {%0,%1,%2,%3}, {%4,%5,%6,%7}, {%8,%9}, {%0,%1,%2,%3};"
        : "+f"(c[0]), "+f"(c[1]), "+f"(c[2]), "+f"(c[3]) : "r"(a[0]), "r"(a[1]), "r"(a[2]), "r"(a[3]), "r"(b0), "r"(b1));
}
__device__ __forceinline__ uint32_t movtrans(uint32_t a) {
    uint32_t d; asm volatile("movmatrix.sync.aligned.m8n8.trans.b16 %0, %1;" : "=r"(d) : "r"(a)); return d;
}
__device__ __forceinline__ uint32_t pack_bf16(float lo, float hi) {
    uint32_t d; asm("cvt.rn.bf16x2.f32 %0, %1, %2;" : "=r"(d) : "f"(hi), "f"(lo)); return d;
}
__device__ __forceinline__ float bf_lo(uint32_t v) { return __uint_as_float(v << 16); }
__device__ __forceinline__ float bf_hi(uint32_t v) { return __uint_as_float(v & 0xffff0000u); }
__device__ __forceinline__ float rbf(float x) { return bf_hi(pack_bf16(0.f, x)); }
__device__ __forceinline__ float ex2(float x) { float y; asm("ex2.approx.ftz.f32 %0, %1;" : "=f"(y) : "f"(x)); return y; }

__device__ __forceinline__ uint4 ld_relaxed4(const uint32_t* p) {
    uint4 v; asm volatile("ld.relaxed.gpu.global.v4.u32 {%0,%1,%2,%3}, [%4];" : "=r"(v.x), "=r"(v.y), "=r"(v.z), "=r"(v.w) : "l"(p) : "memory"); return v;
}
__device__ __forceinline__ uint2 ld_relaxed2(const uint32_t* p) {
    uint2 v; asm volatile("ld.relaxed.gpu.global.v2.u32 {%0,%1}, [%2];" : "=r"(v.x), "=r"(v.y) : "l"(p) : "memory"); return v;
}
__device__ __forceinline__ uint32_t ld_relaxed1(const uint32_t* p) {
    uint32_t v; asm volatile("ld.relaxed.gpu.global.u32 %0, [%1];" : "=r"(v) : "l"(p) : "memory"); return v;
}
__device__ __forceinline__ void st_relaxed4(uint32_t* p, uint32_t a, uint32_t b, uint32_t c, uint32_t d) {
    asm volatile("st.relaxed.gpu.global.v4.u32 [%0], {%1,%2,%3,%4};" :: "l"(p), "r"(a), "r"(b), "r"(c), "r"(d) : "memory");
}
__device__ __forceinline__ void st_relaxed2(uint32_t* p, uint32_t a, uint32_t b) {
    asm volatile("st.relaxed.gpu.global.v2.u32 [%0], {%1,%2};" :: "l"(p), "r"(a), "r"(b) : "memory");
}
__device__ __forceinline__ void st_relaxed1(uint32_t* p, uint32_t a) {
    asm volatile("st.relaxed.gpu.global.u32 [%0], %1;" :: "l"(p), "r"(a) : "memory");
}
__device__ __forceinline__ uint32_t tagf(float v, uint32_t tag) { return (__float_as_uint(v) & ~1u) | tag; }
__device__ __forceinline__ float untag(uint32_t v) { return __uint_as_float(v & ~1u); }
__device__ __forceinline__ uint32_t bad4(const uint4& v, uint32_t tag) { return (v.x ^ tag) | (v.y ^ tag) | (v.z ^ tag) | (v.w ^ tag); }
__device__ __forceinline__ uint2 strip16(const uint4& v) { return make_uint2(__byte_perm(v.x, v.y, 0x7632), __byte_perm(v.z, v.w, 0x7632)); }
__device__ __forceinline__ void poll_again(uint32_t& n, uint32_t backoff) { if (++n > POLL_LIMIT) __trap(); __nanosleep(backoff); }

#define TS(k) do { } while (0)
#define TSM(k) do { } while (0)
#define TSP(k) do { } while (0)

__device__ __noinline__ void gemv_cols(uint32_t sb, int item, uint32_t dst) {
    const int lane = threadIdx.x & 31, warp = threadIdx.x >> 5;
    const int r = warp * 32 + (lane & 7) + ((lane >> 4) << 3);
    const uint32_t a0 = r * 64 + ((((lane >> 3) & 1) ^ ((r >> 1) & 3)) << 4);
    uint32_t xa = sb + SM_X + ((lane >> 2) & 1) * 2064 + warp * 64 + (lane & 3) * 4;
    float acc[4][4] = {};
    int s = item % NSLOT, ph = (item / NSLOT) & 1;
    #pragma unroll 1
    for (int i = 0; i < 4; i++) {
        uint32_t b[4];
        #pragma unroll
        for (int k = 0; k < 4; k++) asm volatile("ld.shared.u32 %0, [%1];" : "=r"(b[k]) : "r"(xa + k * 16));
        xa += 512;
        const uint32_t full = sb + SM_BAR + s * 8, slot = sb + s * SLOT;
        mbar_wait(full, ph);
        uint32_t a[4][4];
        ldsm4t(a[0], slot + a0); ldsm4t(a[1], slot + (a0 ^ 32)); ldsm4t(a[2], slot + a0 + 1024); ldsm4t(a[3], slot + (a0 ^ 32) + 1024);
        mma16816(acc[0], a[0], b[0], b[1]); mma16816(acc[1], a[1], b[0], b[1]);
        mma16816(acc[2], a[2], b[2], b[3]); mma16816(acc[3], a[3], b[2], b[3]);
        __syncwarp();
        if (lane == 0) mbar_arrive(full + NSLOT * 8, 1);
        if (++s == NSLOT) { s = 0; ph ^= 1; }
    }
    const int t = lane & 3;
    const float v0 = (t & 2) ? ((t & 1) ? acc[1][2] + acc[3][2] : acc[1][0] + acc[3][0]) : ((t & 1) ? acc[0][2] + acc[2][2] : acc[0][0] + acc[2][0]);
    const float v1 = (t & 2) ? ((t & 1) ? acc[1][3] + acc[3][3] : acc[1][1] + acc[3][1]) : ((t & 1) ? acc[0][3] + acc[2][3] : acc[0][1] + acc[2][1]);
    asm volatile("st.shared.v2.f32 [%0], {%1, %2};" :: "r"(dst + warp * 256 + (t * 8 + (lane >> 2)) * 8), "f"(v0), "f"(v1) : "memory");
}

__global__ void __launch_bounds__(NTHREADS, 1) fused_decode_kernel(const __grid_constant__ Params p) {
    extern __shared__ char smem_raw[];
    const uint32_t sraw = smem_u32(smem_raw);
    const uint32_t sb = (sraw + 1023) & ~1023u;
    char* sm = smem_raw + (sb - sraw);
    const int tid = threadIdx.x, warp = __shfl_sync(0xffffffffu, tid >> 5, 0), lane = tid & 31;
    const int c = blockIdx.x;
    const int grp = c >> 4, j = c & 15;
    const uint32_t bar_full = sb + SM_BAR, bar_empty = bar_full + NSLOT * 8;

    volatile uint32_t* const issued = reinterpret_cast<volatile uint32_t*>(sm + SM_ISS);
    if (warp == 8) {
        uint64_t pol;
        asm volatile("createpolicy.fractional.L2::evict_first.b64 %0, 1.0;" : "=l"(pol));
        uint32_t t0 = 0;
        if (lane == 0) {
            TSP(16);
            mbar_init(bar_full, 1); mbar_init(bar_full + 8, 1);
            asm volatile("fence.mbarrier_init.release.cluster;" ::: "memory");
            #pragma unroll
            for (int i = 0; i < BURST; i++) {
                mbar_expect_tx(bar_full + i * 8, SLOT);
                tma3d(sb + i * SLOT, &p.m[0], c * 32, i * 256, bar_full + i * 8, pol);
            }
            t0 = gtime32();
            TSP(26);
            #pragma unroll
            for (int s = BURST; s < 2 * NSLOT; s++) mbar_init(bar_full + s * 8, s < NSLOT ? 1 : 8);
            asm volatile("fence.mbarrier_init.release.cluster;" ::: "memory");
            issued[0] = t0; issued[1] = t0; issued[NSLOT] = 0; issued[NSLOT + 1] = 0;
            TSP(27);
        }
        __syncwarp();
        asm volatile("bar.arrive 3, 64;" ::: "memory");
        asm volatile("bar.arrive 2, 288;" ::: "memory");
        if (lane != 0) return;
        TSP(28);
        int s = BURST, ph = 1;
        uint32_t due = t0 + p.opt3 + grp * p.stag_grp + j * p.stag_j;
        const int inflight = p.inflight;
        const uint32_t pace = p.pace_ns, pace78 = (pace * 7) >> 3;
        #pragma unroll 1
        for (int i = BURST; i < N_ITEMS; i++) {
            int mi, c0, c1; uint32_t bytes = SLOT;
            if (i >= IT_KV && i < IT_WU) { mi = 2 + (i & 1); c0 = 0; c1 = grp * 32768 + (((i - IT_KV) >> 1) * 16 + j) * 64; }
            else if (i < IT_WO)          { mi = i < IT_WG ? 0 : i < IT_KV ? 1 : 4; c0 = c * 32; c1 = (i & 3) * 256; if (i >= IT_WG && c >= NFFN) bytes = 0; }
            else if (i < IT_WD)          { mi = 5; c0 = j * 64; c1 = (i & 3) * 1024 + grp * 128; }
            else                         { mi = 6; c0 = j * 64; c1 = (i & 3) * 896 + grp * 112; bytes = 14336; }
            const int ip = i - 1;
            due += ((ip >= IT_WG && ip < IT_KV) || (ip >= IT_WU && ip < IT_WO) || ip >= IT_WD) ? pace78 : pace;
            if (i >= NSLOT) mbar_wait(bar_empty + s * 8, ph);
            uint32_t now, n = 0;
            while (true) {
                uint32_t landed, shift;
                asm volatile("ld.volatile.shared.v2.u32 {%0, %1}, [%2];" : "=r"(landed), "=r"(shift) : "r"(sb + SM_ISS + NSLOT * 4) : "memory");
                now = gtime32();
                if ((int)landed > i - inflight && (int)(now - due - shift) >= 0) break;
                if (++n > (POLL_LIMIT << 4)) __trap();
            }
            issued[s] = now;
            mbar_expect_tx(bar_full + s * 8, bytes);
            if (bytes) tma3d(sb + s * SLOT, &p.m[mi], c0, c1, bar_full + s * 8, pol);
            if (++s == NSLOT) { s = 0; ph ^= 1; }
        }
        return;
    }
    if (warp == 9) {
        asm volatile("bar.sync 3, 64;" ::: "memory");
        const uint32_t t0 = issued[0];
        {
            int s = 0, ph = 0, slow = 0, hold = p.stall_from;
            uint32_t shift = 0;
            const uint32_t stall_lat = p.stall_lat;
            #pragma unroll 1
            for (int i = 0; i < N_ITEMS - 1; i++) {
                mbar_wait(bar_full + s * 8, ph);
                const uint32_t now = gtime32();
                slow = (i >= hold && i < p.stall_to && now - issued[s] > stall_lat) ? slow + 1 : 0;
                if (slow == 2) { shift += p.stall_ns; hold = i + 4; }
                if (lane == 0) asm volatile("st.volatile.shared.v2.u32 [%0], {%1, %2};" :: "r"(sb + SM_ISS + NSLOT * 4), "r"(i + 1), "r"(shift) : "memory");
                if (++s == NSLOT) { s = 0; ph ^= 1; }
            }
        }
        const int e = (lane & 1) * 8 + (lane & 2) * 2 + ((lane & 4) >> 1) + ((lane & 8) >> 3);
        const int oidx = (e & 1) * 1024 + c * 8 + (e >> 1);
        const float xres = __bfloat162float(p.x[oidx]);
        const uint32_t epoch = *reinterpret_cast<volatile uint32_t*>(sm + SM_LN + 64);
        const uint32_t tag1 = (epoch + 1) & 1u;
        const uint32_t* src = &g_pout[c * 256 + lane * 8];
        const bool b1 = lane & 2, b2 = lane & 4, b3 = lane & 8;
        mbar_wait(bar_full + ((N_ITEMS - 1) % NSLOT) * 8, ((N_ITEMS - 1) / NSLOT) & 1);
        TSM(9);
        uint32_t n = 0;
        #pragma unroll 1
        while (true) {
            const uint4 v = ld_relaxed4(src), w = ld_relaxed4(src + 4);
            const bool ok = __all_sync(0xffffffffu, ((bad4(v, tag1) | bad4(w, tag1)) & 1u) == 0);
            float r0 = untag(b1 ? w.x : v.x) + __shfl_xor_sync(0xffffffffu, untag(b1 ? v.x : w.x), 2);
            float r1 = untag(b1 ? w.y : v.y) + __shfl_xor_sync(0xffffffffu, untag(b1 ? v.y : w.y), 2);
            float r2 = untag(b1 ? w.z : v.z) + __shfl_xor_sync(0xffffffffu, untag(b1 ? v.z : w.z), 2);
            float r3 = untag(b1 ? w.w : v.w) + __shfl_xor_sync(0xffffffffu, untag(b1 ? v.w : w.w), 2);
            float s0 = (b2 ? r2 : r0) + __shfl_xor_sync(0xffffffffu, b2 ? r0 : r2, 4);
            float s1 = (b2 ? r3 : r1) + __shfl_xor_sync(0xffffffffu, b2 ? r1 : r3, 4);
            float u = (b3 ? s1 : s0) + __shfl_xor_sync(0xffffffffu, b3 ? s0 : s1, 8);
            u += __shfl_xor_sync(0xffffffffu, u, 16);
            if (ok) {
                if (lane < 16) p.out[oidx] = __float2bfloat16_rn(u + xres);
                break;
            }
            if (++n > POLL_LIMIT) __trap();
        }
        if (c == 0 && lane == 0) st_relaxed1(&g_epoch, epoch + 1);
        TSM(10);
        return;
    }

    TS(0);
    const int g = lane >> 2, t = lane & 3;
    const uint32_t epoch = ld_relaxed1(&g_epoch);
    {
        const uint4 v = __ldg(reinterpret_cast<const uint4*>(p.x) + tid);
        float f[8] = {bf_lo(v.x), bf_hi(v.x), bf_lo(v.y), bf_hi(v.y), bf_lo(v.z), bf_hi(v.z), bf_lo(v.w), bf_hi(v.w)};
        float* sL = reinterpret_cast<float*>(sm + SM_LN);
        float s = ((f[0] + f[1]) + (f[2] + f[3])) + ((f[4] + f[5]) + (f[6] + f[7]));
        #pragma unroll
        for (int o = 16; o > 0; o >>= 1) s += __shfl_xor_sync(0xffffffffu, s, o);
        if (lane == 0) sL[warp] = s;
        asm volatile("bar.sync 2, 288;" ::: "memory");
        const float4 s4 = *reinterpret_cast<const float4*>(sL + (warp & 4));
        const float m = ((s4.x + s4.y) + (s4.z + s4.w)) * (1.0f / 1024.0f);
        float q = 0.f;
        #pragma unroll
        for (int k = 0; k < 8; k++) q += (f[k] - m) * (f[k] - m);
        #pragma unroll
        for (int o = 16; o > 0; o >>= 1) q += __shfl_xor_sync(0xffffffffu, q, o);
        if (lane == 0) sL[8 + warp] = q;
        if (tid == 0) *reinterpret_cast<volatile uint32_t*>(sm + SM_LN + 64) = epoch;
        cbar();
        const float4 q4 = *reinterpret_cast<const float4*>(sL + 8 + (warp & 4));
        const float var = ((q4.x + q4.y) + (q4.z + q4.w)) * (1.0f / 1024.0f);
        const float mb = rbf(m), den = rbf(sqrtf(rbf(rbf(var) + 1e-5f)));
        #pragma unroll
        for (int k = 0; k < 8; k++) f[k] = rbf(f[k] - mb) / den;
        *reinterpret_cast<uint4*>(sm + SM_X + (warp >> 2) * 2064 + (tid & 127) * 16) =
            make_uint4(pack_bf16(f[0], f[1]), pack_bf16(f[2], f[3]), pack_bf16(f[4], f[5]), pack_bf16(f[6], f[7]));
        cbar();
    }
    const uint32_t tag1 = (epoch + 1) & 1u, tag16 = (epoch + 1) & 0xffffu;
    const uint32_t backoff = p.backoff;
    TS(1);
    if ((p.opt2 & 2) && lane == 0 && warp >= 1 && warp < 7) asm volatile("prefetch.tensormap [%0];" :: "l"(&p.m[warp]) : "memory");

    float* sG = reinterpret_cast<float*>(sm + SM_G);
    gemv_cols(sb, 0, sb + SM_G);
    cbar();
    if (tid < 64) {
        float s = 0.f;
        #pragma unroll
        for (int w = 0; w < 8; w++) s += sG[w * 64 + lane * 2 + warp];
        st_relaxed1(&g_q[warp * 4096 + c * 32 + lane], (pack_bf16(0.f, s) & 0xffff0000u) | tag16);
    }
    TS(2);
    uint32_t* const po_dst = &g_po[(c * 8 + warp) * PO_ROW + lane * 4];
    uint32_t* const h_dst = &g_h[(warp & 1) * 4096 + c * 32 + lane];
    uint32_t* const o_dst = &g_o[grp * 1024 + warp * 128 + j * 8 + (lane & 1) * 4];
    uint32_t* const pout_dst = &g_pout[(j * 8 + (warp & 3) * 2 + (t & 1)) * 256 + (grp * 2 + (warp >> 2)) * 16 + g * 2];
    {
        const uint32_t nt = tag16 ^ 1u;
        st_relaxed4(po_dst, nt, nt, nt, nt);
        if (lane < 2) { st_relaxed4(po_dst + 128, nt, nt, nt, nt); st_relaxed4(o_dst, nt, nt, nt, nt); }
        if (t < 2) st_relaxed2(pout_dst, nt, nt);
        if (warp >= 6) st_relaxed1(h_dst, nt);
    }
    gemv_cols(sb, IT_WG, sb + SM_G + 2048);
    TS(11);
    uint32_t qb[8][2];
    {
        const uint32_t* src = &g_q[(grp >> 2) * 4096 + (grp & 3) * 1024 + tid * 4];
        uint4 v; uint32_t n = 0;
        while (v = ld_relaxed4(src), (bad4(v, tag16) & 0xffffu) != 0) poll_again(n, backoff);
        *reinterpret_cast<uint2*>(sm + SM_Q + warp * 272 + lane * 8) = strip16(v);
        cbar();
        const uint32_t* q32 = reinterpret_cast<const uint32_t*>(sm + SM_Q + g * 272) + t;
        #pragma unroll
        for (int ks = 0; ks < 8; ks++) { qb[ks][0] = q32[ks * 8]; qb[ks][1] = q32[ks * 8 + 4]; }
    }
    TS(3);
    constexpr float LOG2E = 1.4426950408889634f;
    constexpr float SCALE = 0.08838834764831845f;
    {
        float o[8][4] = {};
        float m0 = -INFINITY, m1 = -INFINITY, l0 = 0.f, l1 = 0.f;
        const int key = (warp & 3) * 16 + (lane & 7);
        const uint32_t koff = (key + ((lane >> 3) & 1) * 8) * 128, kx = (lane >> 4) ^ (lane & 7);
        const uint32_t voff = (key + (lane >> 4) * 8) * 128,       vx = ((lane >> 3) & 1) ^ (lane & 7);
        int s = (IT_KV + (warp >> 2) * 2) % NSLOT, ph = ((IT_KV + (warp >> 2) * 2) / NSLOT) & 1;
        #pragma unroll 1
        for (int it = 0; it < 16; it++) {
            mbar_wait(bar_full + s * 8, ph);
            float sa[4] = {}, sc[4] = {};
            const uint32_t kb = sb + s * SLOT + koff;
            #pragma unroll
            for (int ks = 0; ks < 8; ks += 2) {
                uint32_t a[4], a2[4];
                ldsm4(a,  kb + (ks >> 2) * 8192 + ((((ks & 3) * 2) ^ kx) << 4));
                ldsm4(a2, kb + (ks >> 2) * 8192 + (((((ks + 1) & 3) * 2) ^ kx) << 4));
                mma16816(sa, a, qb[ks][0], qb[ks][1]);
                mma16816(sc, a2, qb[ks + 1][0], qb[ks + 1][1]);
            }
            __syncwarp();
            if (lane == 0) mbar_arrive(bar_empty + s * 8, 2);
            if (++s == NSLOT) { s = 0; ph ^= 1; }
            uint32_t u0 = pack_bf16(sa[0] + sc[0], sa[1] + sc[1]), u1 = pack_bf16(sa[2] + sc[2], sa[3] + sc[3]);
            u0 = pack_bf16(bf_lo(u0) * SCALE, bf_hi(u0) * SCALE);
            u1 = pack_bf16(bf_lo(u1) * SCALE, bf_hi(u1) * SCALE);
            __nv_bfloat162 mx = __hmax2(*reinterpret_cast<__nv_bfloat162*>(&u0), *reinterpret_cast<__nv_bfloat162*>(&u1));
            #pragma unroll
            for (int off = 4; off < 32; off <<= 1) {
                uint32_t other = __shfl_xor_sync(0xffffffffu, *reinterpret_cast<uint32_t*>(&mx), off);
                mx = __hmax2(mx, *reinterpret_cast<__nv_bfloat162*>(&other));
            }
            const uint32_t mxu = *reinterpret_cast<uint32_t*>(&mx);
            const float n0 = fmaxf(m0, bf_lo(mxu)), n1 = fmaxf(m1, bf_hi(mxu));
            const float al0 = ex2((m0 - n0) * LOG2E), al1 = ex2((m1 - n1) * LOG2E);
            m0 = n0; m1 = n1;
            const float p0 = ex2((bf_lo(u0) - n0) * LOG2E), p1 = ex2((bf_hi(u0) - n1) * LOG2E);
            const float p2 = ex2((bf_lo(u1) - n0) * LOG2E), p3 = ex2((bf_hi(u1) - n1) * LOG2E);
            l0 = l0 * al0 + (p0 + p2); l1 = l1 * al1 + (p1 + p3);
            const uint32_t pb0 = movtrans(pack_bf16(p0, p1)), pb1 = movtrans(pack_bf16(p2, p3));
            #pragma unroll
            for (int mt = 0; mt < 8; mt++) { o[mt][0] *= al0; o[mt][1] *= al1; o[mt][2] *= al0; o[mt][3] *= al1; }
            mbar_wait(bar_full + s * 8, ph);
            const uint32_t vb = sb + s * SLOT + voff;
            #pragma unroll
            for (int mt = 0; mt < 8; mt++) {
                uint32_t a[4];
                ldsm4t(a, vb + (mt >> 2) * 8192 + ((((mt & 3) * 2) ^ vx) << 4));
                mma16816(o[mt], a, pb0, pb1);
            }
            __syncwarp();
            if (lane == 0) mbar_arrive(bar_empty + s * 8, 2);
            s += 3; if (s >= NSLOT) { s -= NSLOT; ph ^= 1; }
        }
        TS(4);
        #pragma unroll
        for (int off = 4; off < 32; off <<= 1) { l0 += __shfl_xor_sync(0xffffffffu, l0, off); l1 += __shfl_xor_sync(0xffffffffu, l1, off); }
        float* sML = reinterpret_cast<float*>(sm + SM_ML);
        float* sR = reinterpret_cast<float*>(sm + SM_RED);
        float* dst = sR + warp * (8 * 132) + (2 * t) * 132 + g;
        #pragma unroll
        for (int mt = 0; mt < 8; mt++) {
            dst[mt * 16] = o[mt][0]; dst[132 + mt * 16] = o[mt][1];
            dst[mt * 16 + 8] = o[mt][2]; dst[132 + mt * 16 + 8] = o[mt][3];
        }
        if (lane < 4) {
            *reinterpret_cast<float2*>(sML + (2 * t) * 16 + warp * 2) = make_float2(m0, l0);
            *reinterpret_cast<float2*>(sML + (2 * t + 1) * 16 + warp * 2) = make_float2(m1, l1);
        }
        cbar();
        float4 ml[4];
        #pragma unroll
        for (int w = 0; w < 4; w++) ml[w] = *reinterpret_cast<const float4*>(sML + warp * 16 + w * 4);
        const float M = fmaxf(fmaxf(fmaxf(ml[0].x, ml[0].z), fmaxf(ml[1].x, ml[1].z)), fmaxf(fmaxf(ml[2].x, ml[2].z), fmaxf(ml[3].x, ml[3].z)));
        float4 a = make_float4(0.f, 0.f, 0.f, 0.f);
        float L = 0.f;
        #pragma unroll
        for (int w = 0; w < 8; w++) {
            const float4 v = *reinterpret_cast<const float4*>(sR + w * (8 * 132) + warp * 132 + lane * 4);
            const float f = ex2((((w & 1) ? ml[w >> 1].z : ml[w >> 1].x) - M) * LOG2E);
            L += ((w & 1) ? ml[w >> 1].w : ml[w >> 1].y) * f;
            a.x += v.x * f; a.y += v.y * f; a.z += v.z * f; a.w += v.w * f;
        }
        st_relaxed4(po_dst, tagf(a.x, tag1), tagf(a.y, tag1), tagf(a.z, tag1), tagf(a.w, tag1));
        if (lane == 0) st_relaxed2(po_dst + 128, tagf(M, tag1), tagf(L, tag1));
    }
    TS(5);
    gemv_cols(sb, IT_WU, sb + SM_G + 4096);
    const uint32_t* const po_src = &g_po[((warp * 16 + (lane >> 1)) * 8 + grp) * PO_ROW];
    uint4 pv = ld_relaxed4(po_src + j * 8 + (lane & 1) * 4);
    uint2 pml = ld_relaxed2(po_src + 128);
    cbar();
    if (warp >= 6) {
        const int src = lane * 2 + (warp & 1);
        float gs = 0.f, us = 0.f;
        #pragma unroll
        for (int w = 0; w < 8; w++) { gs += sG[512 + w * 64 + src]; us += sG[1024 + w * 64 + src]; }
        gs = rbf(gs); us = rbf(us);
        const float inner = 0.7978845608028654f * (gs + 0.044715f * gs * gs * gs);
        const float hv = rbf(0.5f * gs * (1.0f + tanhf(inner))) * us;
        st_relaxed1(h_dst, (pack_bf16(0.f, hv) & 0xffff0000u) | tag16);
    }
    TS(12);
    {
        uint32_t n = 0;
        while (((bad4(pv, tag1) | (pml.x ^ tag1) | (pml.y ^ tag1)) & 1u) != 0) {
            poll_again(n, backoff);
            pv = ld_relaxed4(po_src + j * 8 + (lane & 1) * 4); pml = ld_relaxed2(po_src + 128);
        }
        __syncwarp();
        TS(6);
        const float m = untag(pml.x);
        float M = m;
        #pragma unroll
        for (int off = 2; off < 32; off <<= 1) M = fmaxf(M, __shfl_xor_sync(0xffffffffu, M, off));
        const float f = ex2((m - M) * LOG2E);
        float L = untag(pml.y) * f, a0 = untag(pv.x) * f, a1 = untag(pv.y) * f, a2 = untag(pv.z) * f, a3 = untag(pv.w) * f;
        #pragma unroll
        for (int off = 2; off < 32; off <<= 1) {
            L += __shfl_xor_sync(0xffffffffu, L, off);
            a0 += __shfl_xor_sync(0xffffffffu, a0, off); a1 += __shfl_xor_sync(0xffffffffu, a1, off);
            a2 += __shfl_xor_sync(0xffffffffu, a2, off); a3 += __shfl_xor_sync(0xffffffffu, a3, off);
        }
        const float inv = __fdividef(1.0f, L);
        const uint32_t u01 = pack_bf16(a0 * inv, a1 * inv), u23 = pack_bf16(a2 * inv, a3 * inv);
        if (lane < 2) st_relaxed4(o_dst, (u01 << 16) | tag16, (u01 & 0xffff0000u) | tag16, (u23 << 16) | tag16, (u23 & 0xffff0000u) | tag16);
    }
    TS(14);
    {
        mbar_wait(bar_full + ((IT_WO + p.opt) % NSLOT) * 8, ((IT_WO + p.opt) / NSLOT) & 1);
        const uint32_t* hs = &g_h[(warp >> 2) * 4096 + (warp & 3) * 896 + grp * 112 + min(lane, 27) * 4];
        const uint32_t* os = &g_o[grp * 1024 + tid * 4];
        uint4 vh, vo; uint32_t n = 0;
        while (vh = ld_relaxed4(hs), vo = ld_relaxed4(os), ((bad4(vh, tag16) | bad4(vo, tag16)) & 0xffffu) != 0) poll_again(n, backoff);
        if (lane < 28) *reinterpret_cast<uint2*>(sm + SM_H + (warp >> 2) * 928 + ((warp & 3) * 112 + lane * 4) * 2) = strip16(vh);
        *reinterpret_cast<uint2*>(sm + SM_Q + warp * 272 + lane * 8) = strip16(vo);
        cbar();
    }
    TS(7);
    {
        float acc[4][4] = {};
        const int kh = warp >> 2;
        const uint32_t woff = sb + ((lane & 7) + ((lane >> 4) << 3) + kh * 64) * 128 + ((((warp & 3) * 2 + ((lane >> 3) & 1)) ^ (lane & 7)) << 4);
        uint32_t ba = sb + SM_Q + (g & 1) * (4 * 272) + kh * 128 + t * 4;
        int s = IT_WO % NSLOT, ph = (IT_WO / NSLOT) & 1;
        #pragma unroll 1
        for (int i = 0; i < 8; i++) {
            uint32_t b[8];
            #pragma unroll
            for (int k = 0; k < 8; k++) asm volatile("ld.shared.u32 %0, [%1];" : "=r"(b[k]) : "r"(ba + k * 16));
            ba = i == 3 ? sb + SM_H + (g & 1) * 928 + kh * 128 + t * 4 : ba + (i < 4 ? 272 : 224);
            const bool skip = i >= 4 && kh == 1;
            TS(18 + i);
            mbar_wait(bar_full + s * 8, ph);
            uint32_t a[4][4];
            const uint32_t wa = woff + s * SLOT;
            ldsm4t(a[0], wa); ldsm4t(a[1], wa + 2048); ldsm4t(a[2], wa + 4096); ldsm4t(a[3], wa + (skip ? 4096 : 6144));
            mma16816(acc[0], a[0], b[0], b[1]); mma16816(acc[1], a[1], b[2], b[3]);
            mma16816(acc[2], a[2], b[4], b[5]); mma16816(acc[3], a[3], skip ? 0u : b[6], skip ? 0u : b[7]);
            if (++s == NSLOT) { s = 0; ph ^= 1; }
        }
        const int e = (t & 1) * 2;
        const float v0 = e ? (acc[0][2] + acc[1][2]) + (acc[2][2] + acc[3][2]) : (acc[0][0] + acc[1][0]) + (acc[2][0] + acc[3][0]);
        const float v1 = e ? (acc[0][3] + acc[1][3]) + (acc[2][3] + acc[3][3]) : (acc[0][1] + acc[1][1]) + (acc[2][1] + acc[3][1]);
        if (t < 2) st_relaxed2(pout_dst, tagf(v0, tag1), tagf(v1, tag1));
    }
    TS(8);
}

typedef CUresult (*EncodeFn)(CUtensorMap*, CUtensorMapDataType, cuuint32_t, void*, const cuuint64_t*, const cuuint64_t*,
                             const cuuint32_t*, const cuuint32_t*, CUtensorMapInterleave, CUtensorMapSwizzle,
                             CUtensorMapL2promotion, CUtensorMapFloatOOBfill);

void make_map(EncodeFn enc, CUtensorMap* m, const void* ptr, uint64_t d0, uint64_t d1, uint64_t d2, uint64_t s1, uint64_t s2,
              uint32_t b0, uint32_t b1, uint32_t b2, CUtensorMapSwizzle sw, CUtensorMapL2promotion promo) {
    cuuint64_t dims[3] = {d0, d1, d2};
    cuuint64_t str[2] = {s1, s2};
    cuuint32_t box[3] = {b0, b1, b2};
    cuuint32_t es[3] = {1, 1, 1};
    enc(m, CU_TENSOR_MAP_DATA_TYPE_BFLOAT16, 3, const_cast<void*>(ptr), dims, str, box, es, CU_TENSOR_MAP_INTERLEAVE_NONE, sw, promo,
        CU_TENSOR_MAP_FLOAT_OOB_FILL_NONE);
}

}

extern "C" void kernel_launch(void* const* d_in, const int* in_sizes, int n_in, void* d_out, int out_size) {
    (void)in_sizes; (void)n_in; (void)out_size;
    static EncodeFn enc = nullptr;
    static int pace = 0;
    if (!enc) {
        void* fn = nullptr;
        cudaDriverEntryPointQueryResult st;
        cudaGetDriverEntryPoint("cuTensorMapEncodeTiled", &fn, cudaEnableDefault, &st);
        enc = (EncodeFn)fn;
        cudaFuncSetAttribute(fused_decode_kernel, cudaFuncAttributeMaxDynamicSharedMemorySize, SMEM_BYTES);
        int dev = 0, khz = 0, bits = 0;
        cudaGetDevice(&dev);
        cudaDeviceGetAttribute(&khz, cudaDevAttrMemoryClockRate, dev);
        cudaDeviceGetAttribute(&bits, cudaDevAttrGlobalMemoryBusWidth, dev);
        const double peak = 2.0 * khz * 1e3 * bits / 8.0;
        pace = peak > 0 ? (int)(1e9 * (double)SLOT * NCTA / (0.976 * peak)) : 0;
    }
    Params p;
    CUtensorMapL2promotion pkv = CU_TENSOR_MAP_L2_PROMOTION_L2_256B, pw = CU_TENSOR_MAP_L2_PROMOTION_L2_128B, pt = CU_TENSOR_MAP_L2_PROMOTION_L2_256B;
    p.pace_ns = pace; p.burst = 2; p.inflight = 4; p.backoff = 100; p.opt = 3; p.opt2 = 2; p.opt3 = 0; p.stag_grp = pace / 8; p.stag_j = 0; p.stall_lat = 2100; p.stall_ns = 1200; p.stall_from = 12; p.stall_to = 72;
    const CUtensorMapSwizzle SW128 = CU_TENSOR_MAP_SWIZZLE_128B, SW64 = CU_TENSOR_MAP_SWIZZLE_64B;
    make_map(enc, &p.m[0], d_in[3], 4096, 1024, 1, 8192, 8192 * 1024, 32, 256, 1, SW64, pw);
    make_map(enc, &p.m[1], d_in[6], 3584, 1024, 1, 7168, 7168 * 1024, 32, 256, 1, SW64, pw);
    make_map(enc, &p.m[2], d_in[1], 64, 8 * 32768, 2, 256, 128, 64, 64, 2, SW128, pkv);
    make_map(enc, &p.m[3], d_in[2], 64, 8 * 32768, 2, 256, 128, 64, 64, 2, SW128, pkv);
    make_map(enc, &p.m[4], d_in[7], 3584, 1024, 1, 7168, 7168 * 1024, 32, 256, 1, SW64, pw);
    make_map(enc, &p.m[5], d_in[4], 1024, 4096, 1, 2048, 2048 * 4096, 64, 128, 1, SW128, pt);
    make_map(enc, &p.m[6], d_in[8], 1024, 3584, 1, 2048, 2048 * 3584, 64, 112, 1, SW128, pt);
    p.x = (const __nv_bfloat16*)d_in[0];
    p.out = (__nv_bfloat16*)d_out;
    fused_decode_kernel<<<NCTA, NTHREADS, SMEM_BYTES, cudaStreamPerThread>>>(p);
}
```

```cpp
#include <cuda_runtime.h>
#include <cuda.h>
#include <cuda_bf16.h>
#include <stdint.h>

namespace {

constexpr int NCTA      = 128;
constexpr int NTHREADS  = 320;
constexpr int SLOT      = 16384;
constexpr int NSLOT     = 10;
constexpr int IT_WG     = 4;
constexpr int IT_KV     = 8;
constexpr int IT_WU     = 72;
constexpr int IT_WD     = 76;
constexpr int IT_WO     = 80;
constexpr int IT_FIN    = 82;
constexpr int N_ITEMS   = 86;
constexpr int NFFN      = 112;
constexpr int PO_ROW    = 136;
constexpr uint32_t POLL_LIMIT = 1u << 22;

constexpr int BURST      = 2;
constexpr int INFLIGHT   = 4;
constexpr int START_LEAD = 100;
constexpr int STALL_FROM = 12;
constexpr int STALL_REL  = 750;
constexpr int STALL_ABS  = 2300;
constexpr int STALL_PUSH = 1200;
constexpr int TRIM_AT    = 64;
constexpr int TRIM_TO    = 1250;
constexpr int BACKOFF    = 100;
static_assert(INFLIGHT <= NSLOT - 3 && N_ITEMS - NSLOT <= IT_WD, "ring too small");

constexpr int SM_RED    = NSLOT * SLOT;
constexpr int SM_Q      = SM_RED + 8 * 8 * 132 * 4;
constexpr int SM_G      = SM_Q + 8 * 136 * 2;
constexpr int SM_ML     = SM_G + 3 * 8 * 32 * 2 * 4;
constexpr int SM_B      = SM_ML + 8 * 8 * 2 * 4;
constexpr int SM_B2     = SM_B + 16 * 272;
constexpr int SM_F      = SM_B2 + 64 * 144;
constexpr int SM_X      = SM_F + 8 * 32 * 4;
constexpr int SM_LN     = SM_X + 2 * 1032 * 2;
constexpr int SM_ISS    = SM_LN + 80;
constexpr int SM_BAR    = SM_ISS + 64;
constexpr int SMEM_BYTES = SM_BAR + 2 * NSLOT * 8 + 8 + 1024;

struct Params {
    CUtensorMap m[8];
    const __nv_bfloat16* x;
    const char* wq;
    __nv_bfloat16* out;
    uint32_t pace;
};

__device__ uint32_t g_epoch;
__device__ __align__(128) uint32_t g_q[2 * 4096];
__device__ __align__(128) uint32_t g_h[2 * 4096];
__device__ __align__(128) uint32_t g_o[8 * 1024];
__device__ __align__(128) uint32_t g_po[NCTA * 8 * PO_ROW];
__device__ __align__(128) uint32_t g_pout[64 * 512];

__device__ __forceinline__ uint32_t smem_u32(const void* p) { return (uint32_t)__cvta_generic_to_shared(p); }
__device__ __forceinline__ uint32_t gtime32() { uint32_t t; asm volatile("mov.u32 %0, %globaltimer_lo;" : "=r"(t)); return t; }
__device__ __forceinline__ void mbar_init(uint32_t bar, uint32_t cnt) { asm volatile("mbarrier.init.shared::cta.b64 [%0], %1;" :: "r"(bar), "r"(cnt) : "memory"); }
__device__ __forceinline__ void mbar_expect_tx(uint32_t bar, uint32_t bytes) { asm volatile("mbarrier.arrive.expect_tx.shared::cta.b64 _, [%0], %1;" :: "r"(bar), "r"(bytes) : "memory"); }
__device__ __forceinline__ void mbar_arrive(uint32_t bar, uint32_t cnt) { asm volatile("mbarrier.arrive.shared::cta.b64 _, [%0], %1;" :: "r"(bar), "r"(cnt) : "memory"); }
__device__ __forceinline__ void mbar_wait(uint32_t bar, uint32_t parity) {
    asm volatile("{\n.reg .pred p;\n.reg .u32 n;\nmov.u32 n, 0;\n"
                 "W_LOOP:\nmbarrier.try_wait.parity.shared::cta.b64 p, [%0], %1;\n@p bra W_DONE;\n"
                 "add.u32 n, n, 1;\nsetp.lt.u32 p, n, %2;\n@p bra W_LOOP;\ntrap;\nW_DONE:\n}"
                 :: "r"(bar), "r"(parity), "n"(POLL_LIMIT >> 2) : "memory");
}
__device__ __forceinline__ void tma3d(uint32_t dst, const CUtensorMap* m, int c0, int c1, uint32_t bar, uint64_t pol) {
    asm volatile("cp.async.bulk.tensor.3d.shared::cluster.global.mbarrier::complete_tx::bytes.L2::cache_hint [%0], [%1, {%3, %4, %5}], [%2], %6;"
                 :: "r"(dst), "l"(m), "r"(bar), "r"(c0), "r"(c1), "r"(0), "l"(pol) : "memory");
}
__device__ __forceinline__ void cbar() { asm volatile("bar.sync 1, 256;" ::: "memory"); }

__device__ __forceinline__ void ldsm4(uint32_t (&r)[4], uint32_t a) {
    asm volatile("ldmatrix.sync.aligned.m8n8.x4.shared.b16 {%0,%1,%2,%3}, [%4];" : "=r"(r[0]), "=r"(r[1]), "=r"(r[2]), "=r"(r[3]) : "r"(a) : "memory");
}
__device__ __forceinline__ void ldsm4t(uint32_t (&r)[4], uint32_t a) {
    asm volatile("ldmatrix.sync.aligned.m8n8.x4.trans.shared.b16 {%0,%1,%2,%3}, [%4];" : "=r"(r[0]), "=r"(r[1]), "=r"(r[2]), "=r"(r[3]) : "r"(a) : "memory");
}
__device__ __forceinline__ void mma16816(float (&c)[4], const uint32_t (&a)[4], uint32_t b0, uint32_t b1) {
    asm("mma.sync.aligned.m16n8k16.row.col.f32.bf16.bf16.f32 {%0,%1,%2,%3}, {%4,%5,%6,%7}, {%8,%9}, {%0,%1,%2,%3};"
        : "+f"(c[0]), "+f"(c[1]), "+f"(c[2]), "+f"(c[3]) : "r"(a[0]), "r"(a[1]), "r"(a[2]), "r"(a[3]), "r"(b0), "r"(b1));
}
__device__ __forceinline__ uint32_t movtrans(uint32_t a) {
    uint32_t d; asm volatile("movmatrix.sync.aligned.m8n8.trans.b16 %0, %1;" : "=r"(d) : "r"(a)); return d;
}
__device__ __forceinline__ uint32_t pack_bf16(float lo, float hi) {
    uint32_t d; asm("cvt.rn.bf16x2.f32 %0, %1, %2;" : "=r"(d) : "f"(hi), "f"(lo)); return d;
}
__device__ __forceinline__ float bf_lo(uint32_t v) { return __uint_as_float(v << 16); }
__device__ __forceinline__ float bf_hi(uint32_t v) { return __uint_as_float(v & 0xffff0000u); }
__device__ __forceinline__ float rbf(float x) { return bf_hi(pack_bf16(0.f, x)); }
__device__ __forceinline__ float ex2(float x) { float y; asm("ex2.approx.ftz.f32 %0, %1;" : "=f"(y) : "f"(x)); return y; }

__device__ __forceinline__ uint4 ld_relaxed4(const uint32_t* p) {
    uint4 v; asm volatile("ld.relaxed.gpu.global.v4.u32 {%0,%1,%2,%3}, [%4];" : "=r"(v.x), "=r"(v.y), "=r"(v.z), "=r"(v.w) : "l"(p) : "memory"); return v;
}
__device__ __forceinline__ uint2 ld_relaxed2(const uint32_t* p) {
    uint2 v; asm volatile("ld.relaxed.gpu.global.v2.u32 {%0,%1}, [%2];" : "=r"(v.x), "=r"(v.y) : "l"(p) : "memory"); return v;
}
__device__ __forceinline__ uint32_t ld_relaxed1(const uint32_t* p) {
    uint32_t v; asm volatile("ld.relaxed.gpu.global.u32 %0, [%1];" : "=r"(v) : "l"(p) : "memory"); return v;
}
__device__ __forceinline__ void st_relaxed4(uint32_t* p, uint32_t a, uint32_t b, uint32_t c, uint32_t d) {
    asm volatile("st.relaxed.gpu.global.v4.u32 [%0], {%1,%2,%3,%4};" :: "l"(p), "r"(a), "r"(b), "r"(c), "r"(d) : "memory");
}
__device__ __forceinline__ void st_relaxed2(uint32_t* p, uint32_t a, uint32_t b) {
    asm volatile("st.relaxed.gpu.global.v2.u32 [%0], {%1,%2};" :: "l"(p), "r"(a), "r"(b) : "memory");
}
__device__ __forceinline__ void st_relaxed1(uint32_t* p, uint32_t a) {
    asm volatile("st.relaxed.gpu.global.u32 [%0], %1;" :: "l"(p), "r"(a) : "memory");
}
__device__ __forceinline__ uint32_t tagf(float v, uint32_t tag) { return (__float_as_uint(v) & ~1u) | tag; }
__device__ __forceinline__ float untag(uint32_t v) { return __uint_as_float(v & ~1u); }
__device__ __forceinline__ uint32_t bad4(const uint4& v, uint32_t tag) { return (v.x ^ tag) | (v.y ^ tag) | (v.z ^ tag) | (v.w ^ tag); }
__device__ __forceinline__ uint2 strip16(const uint4& v) { return make_uint2(__byte_perm(v.x, v.y, 0x7632), __byte_perm(v.z, v.w, 0x7632)); }
__device__ __forceinline__ void poll_again(uint32_t& n) { if (++n > POLL_LIMIT) __trap(); __nanosleep(BACKOFF); }

__device__ __forceinline__ void gemv_cols_items(float (&acc)[4][4], uint32_t sb, int item, int i0, int i1) {
    const int lane = threadIdx.x & 31, warp = threadIdx.x >> 5;
    const int r = warp * 32 + (lane & 7) + ((lane >> 4) << 3);
    const uint32_t a0 = r * 64 + ((((lane >> 3) & 1) ^ ((r >> 1) & 3)) << 4);
    uint32_t xa = sb + SM_X + ((lane >> 2) & 1) * 2064 + warp * 64 + (lane & 3) * 4 + i0 * 512;
    int s = (item + i0) % NSLOT, ph = ((item + i0) / NSLOT) & 1;
    #pragma unroll 1
    for (int i = i0; i < i1; i++) {
        uint32_t b[4];
        #pragma unroll
        for (int k = 0; k < 4; k++) asm volatile("ld.shared.u32 %0, [%1];" : "=r"(b[k]) : "r"(xa + k * 16));
        xa += 512;
        const uint32_t full = sb + SM_BAR + s * 8, slot = sb + s * SLOT;
        mbar_wait(full, ph);
        uint32_t a[4][4];
        ldsm4t(a[0], slot + a0); ldsm4t(a[1], slot + (a0 ^ 32)); ldsm4t(a[2], slot + a0 + 1024); ldsm4t(a[3], slot + (a0 ^ 32) + 1024);
        mma16816(acc[0], a[0], b[0], b[1]); mma16816(acc[1], a[1], b[0], b[1]);
        mma16816(acc[2], a[2], b[2], b[3]); mma16816(acc[3], a[3], b[2], b[3]);
        __syncwarp();
        if (lane == 0) mbar_arrive(full + NSLOT * 8, 1);
        if (++s == NSLOT) { s = 0; ph ^= 1; }
    }
}
__device__ __forceinline__ void gemv_cols_store(const float (&acc)[4][4], uint32_t dst) {
    const int lane = threadIdx.x & 31, warp = threadIdx.x >> 5, t = lane & 3;
    const float v0 = (t & 2) ? ((t & 1) ? acc[1][2] + acc[3][2] : acc[1][0] + acc[3][0]) : ((t & 1) ? acc[0][2] + acc[2][2] : acc[0][0] + acc[2][0]);
    const float v1 = (t & 2) ? ((t & 1) ? acc[1][3] + acc[3][3] : acc[1][1] + acc[3][1]) : ((t & 1) ? acc[0][3] + acc[2][3] : acc[0][1] + acc[2][1]);
    asm volatile("st.shared.v2.f32 [%0], {%1, %2};" :: "r"(dst + warp * 256 + (t * 8 + (lane >> 2)) * 8), "f"(v0), "f"(v1) : "memory");
}
__device__ __forceinline__ void gemv_cols(uint32_t sb, int item, uint32_t dst) {
    float acc[4][4] = {};
    gemv_cols_items(acc, sb, item, 0, 4);
    gemv_cols_store(acc, dst);
}
__device__ __forceinline__ void lds128(uint32_t* r, uint32_t a) {
    asm volatile("ld.shared.v4.u32 {%0,%1,%2,%3}, [%4];" : "=r"(r[0]), "=r"(r[1]), "=r"(r[2]), "=r"(r[3]) : "r"(a) : "memory");
}

__global__ void __launch_bounds__(NTHREADS, 1) fused_decode_kernel(const __grid_constant__ Params p) {
    extern __shared__ char smem_raw[];
    if (threadIdx.x < 128) asm volatile("prefetch.global.L2 [%0];" :: "l"(p.wq + (blockIdx.x * 128 + threadIdx.x) * 128));
    const uint32_t sraw = smem_u32(smem_raw);
    const uint32_t sb = (sraw + 1023) & ~1023u;
    char* sm = smem_raw + (sb - sraw);
    const int tid = threadIdx.x, warp = __shfl_sync(0xffffffffu, tid >> 5, 0), lane = tid & 31;
    const int c = blockIdx.x;
    const int grp = c >> 4, j = c & 15;
    const uint32_t bar_full = sb + SM_BAR, bar_empty = bar_full + NSLOT * 8;

    volatile uint32_t* const issued = reinterpret_cast<volatile uint32_t*>(sm + SM_ISS);
    if (warp == 8) {
        uint64_t pol;
        asm volatile("createpolicy.fractional.L2::evict_first.b64 %0, 1.0;" : "=l"(pol));
        uint32_t t0 = 0;
        if (lane == 0) {
            mbar_init(bar_full, 1); mbar_init(bar_full + 8, 1);
            asm volatile("fence.mbarrier_init.release.cluster;" ::: "memory");
            #pragma unroll
            for (int i = 0; i < BURST; i++) {
                mbar_expect_tx(bar_full + i * 8, SLOT);
                tma3d(sb + i * SLOT, &p.m[0], c * 32, i * 256, bar_full + i * 8, pol);
            }
            t0 = gtime32();
            #pragma unroll
            for (int s = BURST; s <= 2 * NSLOT; s++) mbar_init(bar_full + s * 8, (s < NSLOT || s == 2 * NSLOT) ? 1 : 8);
            asm volatile("fence.mbarrier_init.release.cluster;" ::: "memory");
            issued[0] = t0; issued[1] = t0; issued[NSLOT] = 0; issued[NSLOT + 1] = 0;
        }
        __syncwarp();
        asm volatile("bar.arrive 3, 64;" ::: "memory");
        asm volatile("bar.arrive 2, 288;" ::: "memory");
        if (lane != 0) return;
        int s = BURST, ph = 1;
        const uint32_t pace = p.pace, pace78 = (pace * 7) >> 3, stagger = grp * (pace >> 3);
        uint32_t due = t0 - START_LEAD + stagger;
        #pragma unroll 1
        for (int i = BURST; i < IT_FIN; i++) {
            int mi, c0, c1; uint32_t bytes = SLOT;
            if (i >= IT_KV && i < IT_WU) { mi = 2 + (i & 1); c0 = 0; c1 = grp * 32768 + (((i - IT_KV) >> 1) * 16 + j) * 64; }
            else if (i < IT_WD)          { mi = i < IT_WG ? 0 : i < IT_KV ? 1 : 4; c0 = c * 32; c1 = (i & 3) * 256; if (i >= IT_WG && c >= NFFN) bytes = 0; }
            else if (i < IT_WO)          { mi = 5; c0 = j * 64; c1 = (i & 3) * 896 + grp * 112; bytes = 14336; }
            else                         { mi = 6; c0 = j * 64; c1 = (i & 3) * 1024 + grp * 128; }
            const int ip = i - 1;
            due += ((ip >= IT_WG && ip < IT_KV) || (ip >= IT_WU && ip < IT_WO)) ? pace78 : pace;
            if (i >= NSLOT) mbar_wait(bar_empty + s * 8, ph);
            uint32_t now, n = 0;
            while (true) {
                uint32_t landed, shift;
                asm volatile("ld.volatile.shared.v2.u32 {%0, %1}, [%2];" : "=r"(landed), "=r"(shift) : "r"(sb + SM_ISS + NSLOT * 4) : "memory");
                now = gtime32();
                if ((int)landed > i - INFLIGHT && (int)(now - due - shift) >= 0) break;
                if (++n > (POLL_LIMIT << 4)) __trap();
            }
            issued[s] = now;
            mbar_expect_tx(bar_full + s * 8, bytes);
            if (bytes) tma3d(sb + s * SLOT, &p.m[mi], c0, c1, bar_full + s * 8, pol);
            if (++s == NSLOT) { s = 0; ph ^= 1; }
        }
        if (!(c & 1)) {
            due += ((pace * 45) >> 5) - stagger + issued[NSLOT + 1];
            #pragma unroll
            for (int i = IT_FIN; i < N_ITEMS; i++) {
                const uint32_t bar = bar_full + (i % NSLOT) * 8, dst = sb + (i % NSLOT) * SLOT;
                mbar_wait(bar + NSLOT * 8, ((i / NSLOT) & 1) ^ 1);
                const uint32_t bar2 = i == N_ITEMS - 1 ? bar_full + 2 * NSLOT * 8 : bar;
                if (i == N_ITEMS - 1) { mbar_expect_tx(bar, SLOT / 2); mbar_expect_tx(bar2, SLOT / 2); } else mbar_expect_tx(bar, SLOT);
                while ((int)(gtime32() - due) < 0) { }
                tma3d(dst, &p.m[7], c * 8, 2048 + (i - IT_FIN) * 512, bar, pol);
                tma3d(dst + 8192, &p.m[7], c * 8, 2048 + (i - IT_FIN) * 512 + 256, bar2, pol);
                due += pace >> 1;
            }
        }
        return;
    }
    if (warp == 9) {
        const int e = (lane & 7) * 4 + ((lane >> 2) & 2) + (lane >> 4);
        const int oidx = (e & 1) * 1024 + (c & ~1) * 8 + (e >> 1);
        unsigned short xraw;
        asm volatile("ld.global.nc.u16 %0, [%1];" : "=h"(xraw) : "l"(p.x + oidx));
        asm volatile("bar.sync 3, 64;" ::: "memory");
        {
            int s = 0, ph = 0, slow = 0, hold = STALL_FROM;
            uint32_t shift = 0;
            int avg = 0;
            #pragma unroll 1
            for (int i = 0; i < IT_FIN; i++) {
                mbar_wait(bar_full + s * 8, ph);
                const int lat = gtime32() - issued[s];
                if (i == IT_KV) avg = lat;
                slow = (i >= hold && i < IT_WU && lat > min(avg + STALL_REL, STALL_ABS)) ? slow + 1 : 0;
                if (slow == 2) { shift += STALL_PUSH; hold = i + 4; }
                if (i > IT_KV && slow == 0 && (i >= hold || i < STALL_FROM)) avg += (lat - avg) >> (i < 16 ? 2 : 4);
                if (i == TRIM_AT) {
                    const int d = min(max(avg - TRIM_TO, 0), 2000);
                    shift += d; avg -= d; hold = max(hold, i + 3);
                }
                if (lane == 0) asm volatile("st.volatile.shared.v2.u32 [%0], {%1, %2};" :: "r"(sb + SM_ISS + NSLOT * 4), "r"(i + 1), "r"(shift) : "memory");
                if (++s == NSLOT) { s = 0; ph ^= 1; }
            }
        }
        if (!(c & 1)) {
            const uint32_t epoch = *reinterpret_cast<volatile uint32_t*>(sm + SM_LN + 64);
            uint32_t tagm = (epoch + 1) & 1u;
            asm volatile("" : "+r"(tagm));
            const uint32_t* src = &g_pout[(c >> 1) * 512 + lane * 4];
            mbar_wait(bar_full + (IT_FIN % NSLOT) * 8, (IT_FIN / NSLOT) & 1);
            uint32_t n = 0;
            uint4 v0, v1, v2, v3;
            #pragma unroll 1
            while (true) {
                v0 = ld_relaxed4(src); v1 = ld_relaxed4(src + 128); v2 = ld_relaxed4(src + 256); v3 = ld_relaxed4(src + 384);
                if (__all_sync(0xffffffffu, ((bad4(v0, tagm) | bad4(v1, tagm) | bad4(v2, tagm) | bad4(v3, tagm)) & 1u) == 0)) break;
                if (++n > POLL_LIMIT) __trap();
                __nanosleep(32);
            }
            const float r0 = (untag(v0.x) + untag(v1.x)) + (untag(v2.x) + untag(v3.x)), r1 = (untag(v0.y) + untag(v1.y)) + (untag(v2.y) + untag(v3.y));
            const float r2 = (untag(v0.z) + untag(v1.z)) + (untag(v2.z) + untag(v3.z)), r3 = (untag(v0.w) + untag(v1.w)) + (untag(v2.w) + untag(v3.w));
            const bool b3 = lane & 8, b4 = lane & 16;
            const float s0 = (b3 ? r2 : r0) + __shfl_xor_sync(0xffffffffu, b3 ? r0 : r2, 8);
            const float s1 = (b3 ? r3 : r1) + __shfl_xor_sync(0xffffffffu, b3 ? r1 : r3, 8);
            float u = (b4 ? s1 : s0) + __shfl_xor_sync(0xffffffffu, b4 ? s0 : s1, 16) + bf_lo(xraw);
            if (c == 0 && lane == 0) st_relaxed1(&g_epoch, epoch + 1);
            reinterpret_cast<float*>(sm + SM_F)[7 * 32 + e] = u;
            asm volatile("bar.arrive 4, 288;" ::: "memory");
        }
        return;
    }

    const int g = lane >> 2, t = lane & 3;
    const uint32_t epoch = ld_relaxed1(&g_epoch);
    {
        const uint4 v = __ldg(reinterpret_cast<const uint4*>(p.x) + tid);
        float f[8] = {bf_lo(v.x), bf_hi(v.x), bf_lo(v.y), bf_hi(v.y), bf_lo(v.z), bf_hi(v.z), bf_lo(v.w), bf_hi(v.w)};
        float* sL = reinterpret_cast<float*>(sm + SM_LN);
        float s = ((f[0] + f[1]) + (f[2] + f[3])) + ((f[4] + f[5]) + (f[6] + f[7]));
        #pragma unroll
        for (int o = 16; o > 0; o >>= 1) s += __shfl_xor_sync(0xffffffffu, s, o);
        if (lane == 0) sL[warp] = s;
        asm volatile("bar.sync 2, 288;" ::: "memory");
        const float4 s4 = *reinterpret_cast<const float4*>(sL + (warp & 4));
        const float m = ((s4.x + s4.y) + (s4.z + s4.w)) * (1.0f / 1024.0f);
        float q = 0.f;
        #pragma unroll
        for (int k = 0; k < 8; k++) q += (f[k] - m) * (f[k] - m);
        #pragma unroll
        for (int o = 16; o > 0; o >>= 1) q += __shfl_xor_sync(0xffffffffu, q, o);
        if (lane == 0) sL[8 + warp] = q;
        if (tid == 0) *reinterpret_cast<volatile uint32_t*>(sm + SM_LN + 64) = epoch;
        cbar();
        const float4 q4 = *reinterpret_cast<const float4*>(sL + 8 + (warp & 4));
        const float var = ((q4.x + q4.y) + (q4.z + q4.w)) * (1.0f / 1024.0f);
        const float mb = rbf(m), den = rbf(sqrtf(rbf(rbf(var) + 1e-5f)));
        #pragma unroll
        for (int k = 0; k < 8; k++) f[k] = rbf(f[k] - mb) / den;
        *reinterpret_cast<uint4*>(sm + SM_X + (warp >> 2) * 2064 + (tid & 127) * 16) =
            make_uint4(pack_bf16(f[0], f[1]), pack_bf16(f[2], f[3]), pack_bf16(f[4], f[5]), pack_bf16(f[6], f[7]));
        cbar();
    }
    const uint32_t tag1 = (epoch + 1) & 1u, tag16 = (epoch + 1) & 0xffffu;
    if (lane == 0 && warp >= 1) asm volatile("prefetch.tensormap [%0];" :: "l"(&p.m[warp]) : "memory");

    float* sG = reinterpret_cast<float*>(sm + SM_G);
    gemv_cols(sb, 0, sb + SM_G);
    cbar();
    if (tid < 64) {
        float s = 0.f;
        #pragma unroll
        for (int w = 0; w < 8; w++) s += sG[w * 64 + lane * 2 + warp];
        st_relaxed1(&g_q[warp * 4096 + c * 32 + lane], (pack_bf16(0.f, s) & 0xffff0000u) | tag16);
    }
    uint32_t* const po_dst = &g_po[(c * 8 + warp) * PO_ROW + lane * 4];
    uint32_t* const h_dst = &g_h[(warp & 1) * 4096 + c * 32 + lane];
    uint32_t* const o_dst = &g_o[grp * 1024 + warp * 128 + j * 8 + (lane & 1) * 4];
    uint32_t* const pout_dst = &g_pout[(j * 4 + (warp & 3)) * 512 + (grp * 2 + (warp >> 2)) * 32 + ((t & 1) * 8 + g) * 2];
    {
        const uint32_t nt = tag16 ^ 1u;
        st_relaxed4(po_dst, nt, nt, nt, nt);
        if (lane < 2) { st_relaxed4(po_dst + 128, nt, nt, nt, nt); st_relaxed4(o_dst, nt, nt, nt, nt); }
        if (t < 2) st_relaxed2(pout_dst, nt, nt);
        if (warp >= 6) st_relaxed1(h_dst, nt);
    }
    gemv_cols(sb, IT_WG, sb + SM_G + 2048);
    uint32_t qb[8][2];
    {
        const uint32_t* src = &g_q[(grp >> 2) * 4096 + (grp & 3) * 1024 + tid * 4];
        if (c >= NFFN) mbar_wait(bar_full + (IT_KV % NSLOT) * 8, (IT_KV / NSLOT) & 1);
        uint4 v; uint32_t n = 0;
        while (v = ld_relaxed4(src), (bad4(v, tag16) & 0xffffu) != 0) poll_again(n);
        *reinterpret_cast<uint2*>(sm + SM_Q + warp * 272 + lane * 8) = strip16(v);
        cbar();
        const uint32_t* q32 = reinterpret_cast<const uint32_t*>(sm + SM_Q + g * 272) + t;
        #pragma unroll
        for (int ks = 0; ks < 8; ks++) { qb[ks][0] = q32[ks * 8]; qb[ks][1] = q32[ks * 8 + 4]; }
    }
    constexpr float LOG2E = 1.4426950408889634f;
    constexpr float SCALE = 0.08838834764831845f;
    {
        float o[8][4] = {};
        float m0 = -INFINITY, m1 = -INFINITY, l0 = 0.f, l1 = 0.f;
        const int key = (warp & 3) * 16 + (lane & 7);
        const uint32_t koff = (key + ((lane >> 3) & 1) * 8) * 128, kx = (lane >> 4) ^ (lane & 7);
        const uint32_t voff = (key + (lane >> 4) * 8) * 128,       vx = ((lane >> 3) & 1) ^ (lane & 7);
        int s = (IT_KV + (warp >> 2) * 2) % NSLOT, ph = ((IT_KV + (warp >> 2) * 2) / NSLOT) & 1;
        #pragma unroll 1
        for (int it = 0; it < 16; it++) {
            mbar_wait(bar_full + s * 8, ph);
            float sa[4] = {}, sc[4] = {};
            const uint32_t kb = sb + s * SLOT + koff;
            #pragma unroll
            for (int ks = 0; ks < 8; ks += 2) {
                uint32_t a[4], a2[4];
                ldsm4(a,  kb + (ks >> 2) * 8192 + ((((ks & 3) * 2) ^ kx) << 4));
                ldsm4(a2, kb + (ks >> 2) * 8192 + (((((ks + 1) & 3) * 2) ^ kx) << 4));
                mma16816(sa, a, qb[ks][0], qb[ks][1]);
                mma16816(sc, a2, qb[ks + 1][0], qb[ks + 1][1]);
            }
            __syncwarp();
            if (lane == 0) mbar_arrive(bar_empty + s * 8, 2);
            if (++s == NSLOT) { s = 0; ph ^= 1; }
            uint32_t u0 = pack_bf16(sa[0] + sc[0], sa[1] + sc[1]), u1 = pack_bf16(sa[2] + sc[2], sa[3] + sc[3]);
            u0 = pack_bf16(bf_lo(u0) * SCALE, bf_hi(u0) * SCALE);
            u1 = pack_bf16(bf_lo(u1) * SCALE, bf_hi(u1) * SCALE);
            __nv_bfloat162 mx = __hmax2(*reinterpret_cast<__nv_bfloat162*>(&u0), *reinterpret_cast<__nv_bfloat162*>(&u1));
            #pragma unroll
            for (int off = 4; off < 32; off <<= 1) {
                uint32_t other = __shfl_xor_sync(0xffffffffu, *reinterpret_cast<uint32_t*>(&mx), off);
                mx = __hmax2(mx, *reinterpret_cast<__nv_bfloat162*>(&other));
            }
            const uint32_t mxu = *reinterpret_cast<uint32_t*>(&mx);
            const float n0 = fmaxf(m0, bf_lo(mxu)), n1 = fmaxf(m1, bf_hi(mxu));
            const float al0 = ex2((m0 - n0) * LOG2E), al1 = ex2((m1 - n1) * LOG2E);
            m0 = n0; m1 = n1;
            const float p0 = ex2((bf_lo(u0) - n0) * LOG2E), p1 = ex2((bf_hi(u0) - n1) * LOG2E);
            const float p2 = ex2((bf_lo(u1) - n0) * LOG2E), p3 = ex2((bf_hi(u1) - n1) * LOG2E);
            l0 = l0 * al0 + (p0 + p2); l1 = l1 * al1 + (p1 + p3);
            const uint32_t pb0 = movtrans(pack_bf16(p0, p1)), pb1 = movtrans(pack_bf16(p2, p3));
            #pragma unroll
            for (int mt = 0; mt < 8; mt++) { o[mt][0] *= al0; o[mt][1] *= al1; o[mt][2] *= al0; o[mt][3] *= al1; }
            mbar_wait(bar_full + s * 8, ph);
            const uint32_t vb = sb + s * SLOT + voff;
            #pragma unroll
            for (int mt = 0; mt < 8; mt++) {
                uint32_t a[4];
                ldsm4t(a, vb + (mt >> 2) * 8192 + ((((mt & 3) * 2) ^ vx) << 4));
                mma16816(o[mt], a, pb0, pb1);
            }
            __syncwarp();
            if (lane == 0) mbar_arrive(bar_empty + s * 8, 2);
            s += 3; if (s >= NSLOT) { s -= NSLOT; ph ^= 1; }
        }
        #pragma unroll
        for (int off = 4; off < 32; off <<= 1) { l0 += __shfl_xor_sync(0xffffffffu, l0, off); l1 += __shfl_xor_sync(0xffffffffu, l1, off); }
        float* sML = reinterpret_cast<float*>(sm + SM_ML);
        float* sR = reinterpret_cast<float*>(sm + SM_RED);
        float* dst = sR + warp * (8 * 132) + (2 * t) * 132 + g;
        #pragma unroll
        for (int mt = 0; mt < 8; mt++) {
            dst[mt * 16] = o[mt][0]; dst[132 + mt * 16] = o[mt][1];
            dst[mt * 16 + 8] = o[mt][2]; dst[132 + mt * 16 + 8] = o[mt][3];
        }
        if (lane < 4) {
            *reinterpret_cast<float2*>(sML + (2 * t) * 16 + warp * 2) = make_float2(m0, l0);
            *reinterpret_cast<float2*>(sML + (2 * t + 1) * 16 + warp * 2) = make_float2(m1, l1);
        }
        cbar();
        float4 ml[4];
        #pragma unroll
        for (int w = 0; w < 4; w++) ml[w] = *reinterpret_cast<const float4*>(sML + warp * 16 + w * 4);
        const float M = fmaxf(fmaxf(fmaxf(ml[0].x, ml[0].z), fmaxf(ml[1].x, ml[1].z)), fmaxf(fmaxf(ml[2].x, ml[2].z), fmaxf(ml[3].x, ml[3].z)));
        float4 a = make_float4(0.f, 0.f, 0.f, 0.f);
        float L = 0.f;
        #pragma unroll
        for (int w = 0; w < 8; w++) {
            const float4 v = *reinterpret_cast<const float4*>(sR + w * (8 * 132) + warp * 132 + lane * 4);
            const float f = ex2((((w & 1) ? ml[w >> 1].z : ml[w >> 1].x) - M) * LOG2E);
            L += ((w & 1) ? ml[w >> 1].w : ml[w >> 1].y) * f;
            a.x += v.x * f; a.y += v.y * f; a.z += v.z * f; a.w += v.w * f;
        }
        st_relaxed4(po_dst, tagf(a.x, tag1), tagf(a.y, tag1), tagf(a.z, tag1), tagf(a.w, tag1));
        if (lane < 2) st_relaxed4(po_dst + 128, tagf(M, tag1), tagf(L, tag1), tag1, tag1);
    }
    const uint32_t* const po_src = &g_po[((warp * 16 + (lane >> 1)) * 8 + grp) * PO_ROW];
    uint4 pv; uint2 pml;
    {
        float acc[4][4] = {};
        const int split = c < NFFN ? 2 : 4;
        gemv_cols_items(acc, sb, IT_WU, 0, split);
        pv = ld_relaxed4(po_src + j * 8 + (lane & 1) * 4);
        pml = ld_relaxed2(po_src + 128);
        gemv_cols_items(acc, sb, IT_WU, split, 4);
        gemv_cols_store(acc, sb + SM_G + 4096);
    }
    cbar();
    if (warp >= 6) {
        const int src = lane * 2 + (warp & 1);
        float gs = 0.f, us = 0.f;
        #pragma unroll
        for (int w = 0; w < 8; w++) { gs += sG[512 + w * 64 + src]; us += sG[1024 + w * 64 + src]; }
        gs = rbf(gs); us = rbf(us);
        const float inner = 0.7978845608028654f * (gs + 0.044715f * gs * gs * gs);
        const float hv = rbf(0.5f * gs * (1.0f + tanhf(inner))) * us;
        st_relaxed1(h_dst, (pack_bf16(0.f, hv) & 0xffff0000u) | tag16);
    }
    {
        uint32_t n = 0;
        while (((bad4(pv, tag1) | (pml.x ^ tag1) | (pml.y ^ tag1)) & 1u) != 0) {
            poll_again(n);
            pv = ld_relaxed4(po_src + j * 8 + (lane & 1) * 4); pml = ld_relaxed2(po_src + 128);
        }
        __syncwarp();
        const float m = untag(pml.x);
        float M = m;
        #pragma unroll
        for (int off = 2; off < 32; off <<= 1) M = fmaxf(M, __shfl_xor_sync(0xffffffffu, M, off));
        const float f = ex2((m - M) * LOG2E);
        float L = untag(pml.y) * f, a0 = untag(pv.x) * f, a1 = untag(pv.y) * f, a2 = untag(pv.z) * f, a3 = untag(pv.w) * f;
        #pragma unroll
        for (int off = 2; off < 32; off <<= 1) {
            L += __shfl_xor_sync(0xffffffffu, L, off);
            a0 += __shfl_xor_sync(0xffffffffu, a0, off); a1 += __shfl_xor_sync(0xffffffffu, a1, off);
            a2 += __shfl_xor_sync(0xffffffffu, a2, off); a3 += __shfl_xor_sync(0xffffffffu, a3, off);
        }
        const float inv = __fdividef(1.0f, L);
        const uint32_t u01 = pack_bf16(a0 * inv, a1 * inv), u23 = pack_bf16(a2 * inv, a3 * inv);
        if (lane < 2) st_relaxed4(o_dst, (u01 << 16) | tag16, (u01 & 0xffff0000u) | tag16, (u23 << 16) | tag16, (u23 & 0xffff0000u) | tag16);
    }
    {
        const int kh = warp >> 2;
        const bool owner = !(c & 1);
        const uint32_t woff = sb + ((lane & 7) + ((lane >> 4) << 3) + kh * 64) * 128 + ((((warp & 3) * 2 + ((lane >> 3) & 1)) ^ (lane & 7)) << 4);
        const uint32_t wlast = kh ? 4096 : 6144;
        uint32_t A[3][4][4];
        const uint32_t* hs = &g_h[(warp >> 2) * 4096 + (warp & 3) * 896 + grp * 112 + min(lane, 27) * 4];
        const uint32_t* os = &g_o[grp * 1024 + tid * 4];
        const uint32_t* fs = &g_o[((lane >> 4) * 4 + (warp >> 1)) * 1024 + 2 * 128 + (warp & 1) * 64 + (lane & 15) * 4];
        const uint32_t w0 = sb + SM_B + ((warp & 3) * 2 + (warp >> 2)) * 272 + (lane >> 4) * 128 + (lane & 1) * 64 + ((lane >> 1) & 7) * 4;
        uint4 vh, vo, vf[4];
        vo = vf[0] = vf[1] = vf[2] = vf[3] = make_uint4(tag16, tag16, tag16, tag16);
        #pragma unroll
        for (int i = 0; i < 3; i++) {
            if (i == 2) vh = ld_relaxed4(hs);
            mbar_wait(bar_full + ((IT_WD + i) % NSLOT) * 8, ((IT_WD + i) / NSLOT) & 1);
            #pragma unroll
            for (int ks = 0; ks < 4; ks++) ldsm4t(A[i][ks], woff + ((IT_WD + i) % NSLOT) * SLOT + (ks < 3 ? ks * 2048 : wlast));
        }
        uint32_t n = 0;
        while ((bad4(vh, tag16) & 0xffffu) != 0) { poll_again(n); vh = ld_relaxed4(hs); }
        if ((warp & 3) < 2) vo = ld_relaxed4(os);
        {
            const uint2 sh = strip16(vh);
            asm volatile("st.shared.u32 [%0], %1;\nst.shared.u32 [%0+32], %2;" :: "r"(w0), "r"(lane < 28 ? sh.x : 0u), "r"(lane < 28 ? sh.y : 0u) : "memory");
        }
        cbar();
        float acc[4][4] = {};
        uint32_t ba = sb + SM_B + (g & 1) * 272 + kh * 128 + t * 32;
        #pragma unroll
        for (int i = 0; i < 3; i++) {
            uint32_t b[8];
            lds128(b, ba + i * 544); lds128(b + 4, ba + i * 544 + 16);
            #pragma unroll
            for (int ks = 0; ks < 4; ks++) mma16816(acc[ks], A[i][ks], b[ks * 2], b[ks * 2 + 1]);
        }
        ba += 3 * 544;
        #pragma unroll
        for (int i = 3; i < 6; i++) {
            if (i == 4) {
                while ((bad4(vo, tag16) & 0xffffu) != 0) { poll_again(n); vo = ld_relaxed4(os); }
                const uint2 so = strip16(vo);
                asm volatile("st.shared.u32 [%0], %1;\nst.shared.u32 [%0+32], %2;" :: "r"(w0 + 8 * 272), "r"(so.x), "r"(so.y) : "memory");
                cbar();
            }
            if (i == 4 && owner) {
                #pragma unroll
                for (int k = 0; k < 4; k++) vf[k] = ld_relaxed4(fs + (k >> 1) * 128 + (k & 1) * 512);
            }
            uint32_t b[8];
            lds128(b, ba); lds128(b + 4, ba + 16);
            ba += 544;
            const uint32_t wa = woff + ((IT_WD + i) % NSLOT) * SLOT;
            mbar_wait(bar_full + ((IT_WD + i) % NSLOT) * 8, ((IT_WD + i) / NSLOT) & 1);
            uint32_t a[4][4];
            ldsm4t(a[0], wa); ldsm4t(a[1], wa + 2048); ldsm4t(a[2], wa + 4096); ldsm4t(a[3], wa + (i == 3 ? wlast : 6144));
            #pragma unroll
            for (int ks = 0; ks < 4; ks++) mma16816(acc[ks], a[ks], b[ks * 2], b[ks * 2 + 1]);
        }
        const bool hi = t & 1;
        {
            const float v0 = hi ? (acc[0][2] + acc[1][2]) + (acc[2][2] + acc[3][2]) : (acc[0][0] + acc[1][0]) + (acc[2][0] + acc[3][0]);
            const float v1 = hi ? (acc[0][3] + acc[1][3]) + (acc[2][3] + acc[3][3]) : (acc[0][1] + acc[1][1]) + (acc[2][1] + acc[3][1]);
            if (t < 2) st_relaxed2(pout_dst, tagf(v0, tag1), tagf(v1, tag1));
        }
        if (!owner) return;
        while (((bad4(vf[0], tag16) | bad4(vf[1], tag16) | bad4(vf[2], tag16) | bad4(vf[3], tag16)) & 0xffffu) != 0) {
            poll_again(n);
            #pragma unroll
            for (int k = 0; k < 4; k++) vf[k] = ld_relaxed4(fs + (k >> 1) * 128 + (k & 1) * 512);
        }
        #pragma unroll
        for (int k = 0; k < 4; k++) {
            const uint32_t w2 = sb + SM_B2 + warp * 1152 + (k >> 1) * 576 + (lane >> 4) * 288 + (k & 1) * 144 + (lane & 1) * 64 + ((lane >> 1) & 7) * 4;
            const uint2 s0 = strip16(vf[k]);
            asm volatile("st.shared.u32 [%0], %1;\nst.shared.u32 [%0+32], %2;" :: "r"(w2), "r"(s0.x), "r"(s0.y) : "memory");
        }
        __syncwarp();
        if (warp == 7) asm volatile("bar.sync 5, 128;" ::: "memory");
        else if (warp >= 4) asm volatile("bar.arrive 5, 128;" ::: "memory");
        float fa[4][4] = {};
        const uint32_t foff = sb + ((lane & 7) + ((lane >> 4) << 3)) * 32 + ((((lane >> 3) ^ (lane >> 2)) & 1) << 4);
        const uint32_t fb = sb + SM_B2 + (g & 1) * 144 + t * 32;
        #pragma unroll
        for (int i = 0; i < 4; i++) {
            if (i < 3 || warp < 4) {
                uint32_t b[8], a[4][4];
                lds128(b, fb + warp * 1152 + i * 288); lds128(b + 4, fb + warp * 1152 + i * 288 + 16);
                mbar_wait(bar_full + ((IT_FIN + i) % NSLOT) * 8, ((IT_FIN + i) / NSLOT) & 1);
                #pragma unroll
                for (int ks = 0; ks < 4; ks++) ldsm4t(a[ks], foff + ((IT_FIN + i) % NSLOT) * SLOT + warp * 2048 + ks * 512);
                #pragma unroll
                for (int ks = 0; ks < 4; ks++) mma16816(fa[ks], a[ks], b[ks * 2], b[ks * 2 + 1]);
            }
        }
        if (warp < 7) {
            const float v0 = hi ? (fa[0][2] + fa[1][2]) + (fa[2][2] + fa[3][2]) : (fa[0][0] + fa[1][0]) + (fa[2][0] + fa[3][0]);
            const float v1 = hi ? (fa[0][3] + fa[1][3]) + (fa[2][3] + fa[3][3]) : (fa[0][1] + fa[1][1]) + (fa[2][1] + fa[3][1]);
            if (t < 2) *reinterpret_cast<float2*>(sm + SM_F + warp * 128 + (t * 8 + g) * 8) = make_float2(v0, v1);
            asm volatile("bar.arrive 4, 288;" ::: "memory");
            return;
        }
        uint32_t b[4][8];
        #pragma unroll
        for (int w = 0; w < 4; w++) { lds128(b[w], fb + (4 + w) * 1152 + 3 * 288); lds128(b[w] + 4, fb + (4 + w) * 1152 + 3 * 288 + 16); }
        __nv_bfloat16* const dst = p.out + (t >> 1) * 1024 + c * 8 + (t & 1) * 8 + g;
        const float* sF = reinterpret_cast<const float*>(sm + SM_F) + ((t & 1) * 8 + g) * 2 + (t >> 1);
        mbar_wait(bar_full + 2 * NSLOT * 8, 0);
        #pragma unroll
        for (int w = 0; w < 4; w++) {
            uint32_t a[4][4];
            #pragma unroll
            for (int ks = 0; ks < 4; ks++) ldsm4t(a[ks], foff + ((N_ITEMS - 1) % NSLOT) * SLOT + (4 + w) * 2048 + ks * 512);
            #pragma unroll
            for (int ks = 0; ks < 4; ks++) mma16816(fa[ks], a[ks], b[w][ks * 2], b[w][ks * 2 + 1]);
        }
        asm volatile("bar.sync 4, 288;" ::: "memory");
        const float rest = ((sF[0] + sF[32]) + (sF[64] + sF[96])) + ((sF[128] + sF[160]) + (sF[192] + sF[224]));
        float r[4];
        #pragma unroll
        for (int k = 0; k < 4; k++) r[k] = (t & 2) ? (hi ? fa[k][3] : fa[k][1]) : (hi ? fa[k][2] : fa[k][0]);
        *dst = __float2bfloat16_rn(((r[0] + r[1]) + (r[2] + r[3])) + rest);
    }
}

typedef CUresult (*EncodeFn)(CUtensorMap*, CUtensorMapDataType, cuuint32_t, void*, const cuuint64_t*, const cuuint64_t*,
                             const cuuint32_t*, const cuuint32_t*, CUtensorMapInterleave, CUtensorMapSwizzle,
                             CUtensorMapL2promotion, CUtensorMapFloatOOBfill);

void make_map(EncodeFn enc, CUtensorMap* m, const void* ptr, uint64_t d0, uint64_t d1, uint64_t d2, uint64_t s1, uint64_t s2,
              uint32_t b0, uint32_t b1, uint32_t b2, CUtensorMapSwizzle sw, CUtensorMapL2promotion promo) {
    cuuint64_t dims[3] = {d0, d1, d2};
    cuuint64_t str[2] = {s1, s2};
    cuuint32_t box[3] = {b0, b1, b2};
    cuuint32_t es[3] = {1, 1, 1};
    enc(m, CU_TENSOR_MAP_DATA_TYPE_BFLOAT16, 3, const_cast<void*>(ptr), dims, str, box, es, CU_TENSOR_MAP_INTERLEAVE_NONE, sw, promo,
        CU_TENSOR_MAP_FLOAT_OOB_FILL_NONE);
}

}

extern "C" void kernel_launch(void* const* d_in, const int* in_sizes, int n_in, void* d_out, int out_size) {
    (void)in_sizes; (void)n_in; (void)out_size;
    static EncodeFn enc = nullptr;
    static uint32_t pace = 0;
    if (!enc) {
        void* fn = nullptr;
        cudaDriverEntryPointQueryResult st;
        cudaGetDriverEntryPoint("cuTensorMapEncodeTiled", &fn, cudaEnableDefault, &st);
        enc = (EncodeFn)fn;
        cudaFuncSetAttribute(fused_decode_kernel, cudaFuncAttributeMaxDynamicSharedMemorySize, SMEM_BYTES);
        int dev = 0, khz = 0, bits = 0;
        cudaGetDevice(&dev);
        cudaDeviceGetAttribute(&khz, cudaDevAttrMemoryClockRate, dev);
        cudaDeviceGetAttribute(&bits, cudaDevAttrGlobalMemoryBusWidth, dev);
        const double peak = 2.0 * khz * 1e3 * bits / 8.0;
        pace = peak > 0 ? (uint32_t)(1e9 * (double)SLOT * NCTA / (0.9765 * peak)) : 0;
    }
    const CUtensorMapSwizzle SW128 = CU_TENSOR_MAP_SWIZZLE_128B, SW64 = CU_TENSOR_MAP_SWIZZLE_64B, SW32 = CU_TENSOR_MAP_SWIZZLE_32B;
    const CUtensorMapL2promotion P128 = CU_TENSOR_MAP_L2_PROMOTION_L2_128B, P256 = CU_TENSOR_MAP_L2_PROMOTION_L2_256B;
    Params p;
    make_map(enc, &p.m[0], d_in[3], 4096, 1024, 1, 8192, 8192 * 1024, 32, 256, 1, SW64, P128);
    make_map(enc, &p.m[1], d_in[6], 3584, 1024, 1, 7168, 7168 * 1024, 32, 256, 1, SW64, P128);
    make_map(enc, &p.m[2], d_in[1], 64, 8 * 32768, 2, 256, 128, 64, 64, 2, SW128, P256);
    make_map(enc, &p.m[3], d_in[2], 64, 8 * 32768, 2, 256, 128, 64, 64, 2, SW128, P256);
    make_map(enc, &p.m[4], d_in[7], 3584, 1024, 1, 7168, 7168 * 1024, 32, 256, 1, SW64, P128);
    make_map(enc, &p.m[5], d_in[8], 1024, 3584, 1, 2048, 2048 * 3584, 64, 112, 1, SW128, P256);
    make_map(enc, &p.m[6], d_in[4], 1024, 4096, 1, 2048, 2048 * 4096, 64, 128, 1, SW128, P256);
    make_map(enc, &p.m[7], d_in[4], 1024, 4096, 1, 2048, 2048 * 4096, 16, 256, 1, SW32, P128);
    p.x = (const __nv_bfloat16*)d_in[0];
    p.wq = (const char*)d_in[3];
    p.out = (__nv_bfloat16*)d_out;
    p.pace = pace;
    fused_decode_kernel<<<NCTA, NTHREADS, SMEM_BYTES, cudaStreamPerThread>>>(p);
}
```
